```python
import torch

def _softmax(x, axis=-1):
    return torch.softmax(x, dim=axis)
def _gelu(x):
    return torch.nn.functional.gelu(x, approximate="tanh")
def _silu(x):
    return torch.nn.functional.silu(x)
def _sigmoid(x):
    return torch.sigmoid(x)
def _layernorm(x, axis=-1, eps=1e-5):
    m = x.mean(dim=axis, keepdim=True)
    v = x.var(dim=axis, keepdim=True, unbiased=False)
    return (x - m) / torch.sqrt(v + eps)
def _scatter_add(tgt, idx, src, axis=0):
    return tgt.clone().index_add_(axis, idx, src)
def _segment_sum(src, seg, n):
    out = torch.zeros((n,) + src.shape[1:], dtype=src.dtype)
    return out.index_add_(0, seg, src)
def _pad(x, pw):
    flat = tuple(v for pair in reversed(pw) for v in pair)
    return torch.nn.functional.pad(x, flat)

kernel_name = 'gather_scatter__edge_featured_mpnn_gatedgcn__graph'

def setup_inputs():

    _w = (lambda a: (lambda t: t.to(torch.bfloat16) if t.is_floating_point() else t)(torch.as_tensor(a)))
    N, deg, D, De = 50000, 16, 64, max(0, 1)
    E = N * deg
    return {
        "x": _w((lambda *s: torch.randn(*s, dtype=torch.bfloat16) * 0.4)(N, D)),
        "e_attr": _w((lambda *s: torch.randn(*s, dtype=torch.bfloat16) * 0.8)(E, De)),
        "src": _w((lambda lo, hi, *s: torch.randint(lo, hi, s))(0, N, E).to(torch.int64)),
        "dst": _w((lambda lo, hi, *s: torch.randint(lo, hi, s))(0, N, E).to(torch.int64)),
        "w_a": _w((lambda *s: torch.randn(*s, dtype=torch.bfloat16) * 0.8)(D, D)),
        "w_b": _w((lambda *s: torch.randn(*s, dtype=torch.bfloat16) * 0.4)(D, D)),
        "w_c": _w((lambda *s: torch.randn(*s, dtype=torch.bfloat16) * 0.8)(De, D)),
        "w_u": _w((lambda *s: torch.randn(*s, dtype=torch.bfloat16) * 0.05)(D, D)),
        "w_v": _w((lambda *s: torch.randn(*s, dtype=torch.bfloat16) * 0.05)(D, D)),
    }

def reference(x, e_attr, src, dst, w_a, w_b, w_c, w_u, w_v):
    N, D = x.shape
    hv = x @ w_v
    g = x[dst] @ w_a + x[src] @ w_b + e_attr @ w_c
    eta = _sigmoid(g)
    denom = _segment_sum(eta, dst, N) + 1e-6
    eta_n = eta / denom[dst]
    agg = _segment_sum(eta_n * hv[src], dst, N)
    z = x @ w_u + agg
    relu_z = torch.where(z > 0, z, 0 * z)
    return x + relu_z
```

```cpp
#include <cuda_runtime.h>
#include <cuda.h>
#include <cuda_bf16.h>
#include <cuda_fp16.h>
#include <stdint.h>

namespace {

constexpr int NN = 50000, NE = 800000;
constexpr int NB = 132;
constexpr int NPB = 379;
constexpr int CH = 6064;
constexpr int NU = 2110;
constexpr int NTHR = 896;
constexpr int NMAIN = 768;
constexpr int NG = 384, NEG = 384;
constexpr int LPS = 17;
constexpr int NSPARE = 192;
constexpr int CAPD = 42;
constexpr int NTASK = 95;
constexpr float LOG2E = 1.4426950408889634f;
constexpr int SPIN_LIMIT = 1 << 21;
constexpr int WIN = 4;
constexpr int XE = 2;

constexpr int ROWS = 380 * 128;
constexpr int OFF_WAU = 0;
constexpr int OFF_X = 16384;
constexpr int OFF_LIST = OFF_X + 384 * 128;
constexpr int OFF_WBV = OFF_LIST;
constexpr int OFF_STG = OFF_LIST + 16384;
constexpr int OFF_STD = OFF_STG + NU * 12;
constexpr int OFF_HIST = OFF_STG + NU * 16;
constexpr int OFF_OFFS = OFF_HIST + 320 * 4;
constexpr int OFF_A = (OFF_LIST + 380 * CAPD * 4 + 64 + 127) / 128 * 128;
constexpr int OFF_U = OFF_A + ROWS;
constexpr int OFF_SRC = OFF_U;
constexpr int OFF_EAT = OFF_U + CH * 4;
constexpr int OFF_CNT = OFF_U + ROWS;
constexpr int OFF_DEG = OFF_CNT + 64 * 4;
constexpr int OFF_NINFO = OFF_DEG + 416 * 4;
constexpr int OFF_SEG = OFF_NINFO + 384 * 4;
constexpr int OFF_SPARE = OFF_SEG + NB * 8;
constexpr int OFF_MISC = OFF_SPARE + NSPARE * 4;
constexpr int OFF_WC = OFF_MISC + 64;
constexpr int OFF_MBAR = OFF_WC + 128;
constexpr int SMEM_BYTES = OFF_MBAR + 128;
static_assert(OFF_OFFS + 320 * 4 <= OFF_A, "staging must fit the list region");
static_assert(OFF_A % 128 == 0 && OFF_SEG % 8 == 0 && OFF_WC % 16 == 0, "alignment");
static_assert(NU * 3 >= CH + 2 * NB, "exchange capacity");
static_assert(SMEM_BYTES <= 232448, "smem");
enum { M_TASK = 0, M_XMAX, M_WVMAX, M_BAD, M_SLOW, M_TBAD, M_NSPARE, M_EPOCH, M_GBAD, M_WCMAX, M_NSC, M_EPS };

constexpr size_t TAB_BYTES = (size_t)NN * 192;
__device__ __align__(128) uint4 g_tab[TAB_BYTES / 16];
__device__ __align__(128) uint4 g_xch[NB * NU];
__device__ __align__(128) unsigned long long g_hdr[NB * NB];
__device__ __align__(128) uint32_t g_bar[64];

template <int ID, int N> __device__ __forceinline__ void bar_arrive() { asm volatile("bar.arrive %0, %1;" :: "n"(ID), "n"(N) : "memory"); }
template <int ID, int N> __device__ __forceinline__ void bar_sync() { asm volatile("bar.sync %0, %1;" :: "n"(ID), "n"(N) : "memory"); }
__device__ __forceinline__ uint4 ld_unit(const uint4* p) {
    uint4 v;
    asm volatile("{.reg .b128 t; .reg .b64 a, b; ld.relaxed.gpu.global.b128 t, [%4]; mov.b128 {a, b}, t; mov.b64 {%0, %1}, a; mov.b64 {%2, %3}, b;}"
        : "=r"(v.x), "=r"(v.y), "=r"(v.z), "=r"(v.w) : "l"(p) : "memory");
    return v;
}
__device__ __forceinline__ void st_unit(uint4* p, uint4 v) {
    asm volatile("{.reg .b128 t; .reg .b64 a, b; mov.b64 a, {%1, %2}; mov.b64 b, {%3, %4}; mov.b128 t, {a, b}; st.relaxed.gpu.global.b128 [%0], t;}"
        :: "l"(p), "r"(v.x), "r"(v.y), "r"(v.z), "r"(v.w) : "memory");
}
__device__ __forceinline__ void mbar_wait(uint32_t bar) {
    uint32_t done;
    int spin = 0;
    do {
        asm volatile("{.reg .pred p; mbarrier.try_wait.parity.shared::cta.b64 p, [%1], 0; selp.u32 %0, 1, 0, p;}"
            : "=r"(done) : "r"(bar) : "memory");
    } while (!done && ++spin < SPIN_LIMIT);
}
__device__ __forceinline__ void bulk_load(uint32_t dst, const void* src, uint32_t bytes, uint32_t bar) {
    asm volatile("cp.async.bulk.shared::cluster.global.mbarrier::complete_tx::bytes [%0], [%1], %2, [%3];"
        :: "r"(dst), "l"(src), "r"(bytes), "r"(bar) : "memory");
}
__device__ __forceinline__ void mbar_expect(uint32_t bar, uint32_t bytes) {
    asm volatile("mbarrier.arrive.expect_tx.shared::cta.b64 _, [%0], %1;" :: "r"(bar), "r"(bytes) : "memory");
}
__device__ __forceinline__ float ex2(float x) { float y; asm("ex2.approx.ftz.f32 %0, %1;" : "=f"(y) : "f"(x)); return y; }
__device__ __forceinline__ uint32_t packbf(float lo, float hi) { uint32_t r; asm("cvt.rn.bf16x2.f32 %0, %1, %2;" : "=r"(r) : "f"(hi), "f"(lo)); return r; }
__device__ __forceinline__ uint32_t packh(float lo, float hi) { uint32_t r; asm("cvt.rn.f16x2.f32 %0, %1, %2;" : "=r"(r) : "f"(hi), "f"(lo)); return r; }
__device__ __forceinline__ float bflo(uint32_t w) { return __uint_as_float(w << 16); }
__device__ __forceinline__ float bfhi(uint32_t w) { return __uint_as_float(w & 0xFFFF0000u); }
__device__ __forceinline__ float rbf(float v) { return __bfloat162float(__float2bfloat16_rn(v)); }
__device__ __forceinline__ float hlo(uint32_t w) { return __low2float(*(__half2*)&w); }
__device__ __forceinline__ float hhi(uint32_t w) { return __high2float(*(__half2*)&w); }
__device__ __forceinline__ uint32_t hfma2(uint32_t a, uint32_t b, uint32_t c) { uint32_t d; asm("fma.rn.bf16x2 %0, %1, %2, %3;" : "=r"(d) : "r"(a), "r"(b), "r"(c)); return d; }
__device__ __forceinline__ uint32_t hfma2relu(uint32_t a, uint32_t b, uint32_t c) { uint32_t d; asm("fma.rn.relu.bf16x2 %0, %1, %2, %3;" : "=r"(d) : "r"(a), "r"(b), "r"(c)); return d; }
__device__ __forceinline__ uint32_t hmul2(uint32_t a, uint32_t b) { uint32_t d; asm("mul.rn.bf16x2 %0, %1, %2;" : "=r"(d) : "r"(a), "r"(b)); return d; }
__device__ __forceinline__ uint32_t prmt(uint32_t a, uint32_t b, uint32_t c) { uint32_t d; asm("prmt.b32 %0, %1, %2, %3;" : "=r"(d) : "r"(a), "r"(b), "r"(c)); return d; }
__device__ __forceinline__ uint32_t hadd2(uint32_t a, uint32_t b) { uint32_t d; asm("add.rn.bf16x2 %0, %1, %2;" : "=r"(d) : "r"(a), "r"(b)); return d; }
__device__ __forceinline__ uint32_t magmax2(uint32_t m, uint32_t w) { return __vmaxu2(m, w & 0x7FFF7FFFu); }
__device__ __forceinline__ uint32_t fold2(uint32_t m) { return max(m & 0xFFFFu, m >> 16); }

__device__ __forceinline__ uint32_t nrcp2(uint32_t S) {
    uint32_t R0 = 0xFEF4FEF4u - S;
    uint32_t E = hfma2(S, R0, 0x3F803F80u);
    E = hfma2(E, E, E);
    return hfma2(R0, E, R0);
}

#define R8(c, d, b) c(d[b+0]), c(d[b+1]), c(d[b+2]), c(d[b+3]), c(d[b+4]), c(d[b+5]), c(d[b+6]), c(d[b+7])
#define D32 "{%0,%1,%2,%3,%4,%5,%6,%7,%8,%9,%10,%11,%12,%13,%14,%15,%16,%17,%18,%19,%20,%21,%22,%23,%24,%25,%26,%27,%28,%29,%30,%31}"
template <bool FIRST> __device__ __forceinline__ void gemm_issue(float* d, uint32_t xsm, uint32_t wsm, uint32_t zero) {
    const uint64_t hi = (1ull << 16) | (64ull << 32) | (1ull << 62);
    const uint64_t da = hi | (xsm >> 4), db = hi | (wsm >> 4);
    asm volatile("wgmma.fence.sync.aligned;" ::: "memory");
    if (FIRST)
        asm volatile("wgmma.mma_async.sync.aligned.m64n64k16.f32.bf16.bf16 " D32 ", %32, %33, 0, 1, 1, 0, 1;"
            : R8("=f", d, 0), R8("=f", d, 8), R8("=f", d, 16), R8("=f", d, 24) : "l"(da), "l"(db));
    else
        asm volatile("{.reg .pred p; setp.ne.u32 p, %34, 0; wgmma.mma_async.sync.aligned.m64n64k16.f32.bf16.bf16 " D32 ", %32, %33, p, 1, 1, 0, 1;}"
            : R8("+f", d, 0), R8("+f", d, 8), R8("+f", d, 16), R8("+f", d, 24) : "l"(da), "l"(db), "r"(zero));
    #pragma unroll
    for (int kk = 1; kk < 4; kk++)
        asm volatile("wgmma.mma_async.sync.aligned.m64n64k16.f32.bf16.bf16 " D32 ", %32, %33, 1, 1, 1, 0, 1;"
            : R8("+f", d, 0), R8("+f", d, 8), R8("+f", d, 16), R8("+f", d, 24) : "l"(da + kk * 2), "l"(db + kk * 128));
    asm volatile("wgmma.commit_group.sync.aligned;" ::: "memory");
}
__device__ __forceinline__ void gemm_wait(float* d) {
    asm volatile("wgmma.wait_group.sync.aligned 0;" ::: "memory");
    asm volatile("" : R8("+f", d, 0), R8("+f", d, 8), R8("+f", d, 16), R8("+f", d, 24) :: "memory");
}

struct Row { uint32_t lb0, lb1, lv0, lv1, hb, hv; };
__device__ __forceinline__ void ldrow(Row& r, uint32_t w, bool v, uint64_t pa, uint64_t pb) {
    const uint32_t i = w >> 16;
    asm volatile("{.reg .pred p; setp.ne.u32 p, %8, 0;\n"
                 " @p ld.global.v4.u32 {%0,%1,%2,%3}, [%6];\n @p ld.global.v2.u32 {%4,%5}, [%7];}"
        : "+r"(r.lb0), "+r"(r.lb1), "+r"(r.lv0), "+r"(r.lv1), "+r"(r.hb), "+r"(r.hv)
        : "l"(pa + (uint64_t)i * 128), "l"(pb + (uint64_t)i * 64), "r"((uint32_t)v));
}
__device__ __forceinline__ void unpack(const Row& r, uint32_t* eb, uint32_t* vv) {
    uint32_t hb0 = r.hb & 0x0F0F0F0Fu, hb1 = (r.hb >> 4) & 0x0F0F0F0Fu;
    uint32_t hv0 = r.hv & 0x87878787u, hv1 = __funnelshift_r(r.hv, r.hv, 4) & 0x87878787u;
    eb[0] = __byte_perm(r.lb0, hb0, 0x5140); eb[1] = __byte_perm(r.lb0, hb0, 0x7362);
    eb[2] = __byte_perm(r.lb1, hb1, 0x5140); eb[3] = __byte_perm(r.lb1, hb1, 0x7362);
    vv[0] = __byte_perm(r.lv0, hv0, 0x5140); vv[1] = __byte_perm(r.lv0, hv0, 0x7362);
    vv[2] = __byte_perm(r.lv1, hv1, 0x5140); vv[3] = __byte_perm(r.lv1, hv1, 0x7362);
    asm volatile("" : "+r"(eb[0]), "+r"(eb[1]), "+r"(eb[2]), "+r"(eb[3]), "+r"(vv[0]), "+r"(vv[1]), "+r"(vv[2]), "+r"(vv[3]));
}
__device__ __forceinline__ void gate_t(uint32_t* T, float e, const float* wc, const float* ap) {
    #pragma unroll
    for (int i = 0; i < 4; i++) T[i] = packbf(ex2(fmaf(e, wc[2 * i], ap[2 * i])), ex2(fmaf(e, wc[2 * i + 1], ap[2 * i + 1])));
    asm volatile("" : "+r"(T[0]), "+r"(T[1]), "+r"(T[2]), "+r"(T[3]));
}
__device__ __forceinline__ void gate_rest(const uint32_t* T, const uint32_t* eb, const uint32_t* vv, uint32_t* num, uint32_t* den) {
    #pragma unroll
    for (int i = 0; i < 4; i++) {
        const uint32_t R = nrcp2(hfma2(T[i], eb[i], 0x08000800u));
        den[i] = hadd2(den[i], R);
        num[i] = hfma2(R, vv[i], num[i]);
    }
}

__device__ __forceinline__ void store_rows(unsigned char* base, const uint32_t* a, int row, int q) {
    const uint32_t so = row * 128 + (((2 * q) ^ (row & 7)) << 4);
    #pragma unroll
    for (int h = 0; h < 2; h++) {
        if (row + h * 8 < NPB) {
            *(uint4*)(base + h * 1024 + so) = make_uint4(a[8 * h], a[8 * h + 1], a[8 * h + 2], a[8 * h + 3]);
            *(uint4*)(base + h * 1024 + (so ^ 16)) = make_uint4(a[8 * h + 4], a[8 * h + 5], a[8 * h + 6], a[8 * h + 7]);
        }
    }
}

__device__ __forceinline__ void stg128(void* p, uint32_t a, uint32_t b, uint32_t c, uint32_t d, bool v) {
    asm volatile("{.reg .pred p; setp.ne.u32 p, %5, 0; @p st.global.v4.u32 [%0], {%1, %2, %3, %4};}"
        :: "l"(p), "r"(a), "r"(b), "r"(c), "r"(d), "r"((uint32_t)v) : "memory");
}

__device__ __forceinline__ int table_scale(const uint32_t* misc) {
    const float p = 32.f * bflo(misc[M_XMAX]) * bflo(misc[M_WVMAX]);
    return min(max((int)(__float_as_uint(p) >> 23) - 126, -60), 15);
}

__device__ __forceinline__ void consume(unsigned char* smem, uint4 en, uint32_t ua, int lo8, uint32_t tag) {
    int spin = 0;
    while ((en.w >> 25) != tag) {
        if (++spin >= SPIN_LIMIT) return;
        en = ld_unit(g_xch + ua);
    }
    uint32_t* deg = (uint32_t*)(smem + OFF_DEG);
    uint32_t* list = (uint32_t*)(smem + OFF_LIST);
    uint32_t hb;
    asm("shl.b32 %0, 0x010101, %1;" : "=r"(hb) : "r"(max(lo8, 0)));
    const uint32_t n0 = prmt(en.w, hb, 0xCC40), n1 = prmt(en.w, hb, 0xCC51), n2 = prmt(en.w, hb, 0xCC62);
    const uint32_t r0 = atomicAdd(&deg[n0], 1), r1 = atomicAdd(&deg[n1], 1), r2 = atomicAdd(&deg[n2], 1);
    if (r0 < CAPD) list[n0 * CAPD + r0] = en.x;
    if (r1 < CAPD) list[n1 * CAPD + r1] = en.y;
    if (r2 < CAPD) list[n2 * CAPD + r2] = en.z;
}

__device__ __forceinline__ float gate(float a, float b, float c) { return 1.f / (1.f + expf(-rbf(rbf(a + rbf(b)) + rbf(c)))); }
__device__ __forceinline__ uint32_t finish(uint32_t xw, float u0, float u1, const float* acc, int lane) {
    const float z0 = u0 + acc[64 + lane] / (acc[lane] + 1e-6f), z1 = u1 + acc[96 + lane] / (acc[32 + lane] + 1e-6f);
    return packbf(bflo(xw) + (z0 > 0.f ? z0 : 0.f * z0), bfhi(xw) + (z1 > 0.f ? z1 : 0.f * z1));
}

__device__ __noinline__ void general_path(unsigned char* smem,
                                          const uint32_t* __restrict__ x, const uint32_t* __restrict__ wa,
                                          const uint32_t* __restrict__ wb, const uint32_t* __restrict__ wc,
                                          const uint32_t* __restrict__ wv, uint32_t* __restrict__ out) {
    const int tid = threadIdx.x, lane = tid & 31, warp = tid >> 5;
    const int nbase = blockIdx.x * NPB, nloc = min(NPB, NN - nbase);
    const bool all = ((const uint32_t*)(smem + OFF_MISC))[M_BAD] | ((const uint32_t*)(smem + OFF_MISC))[M_GBAD];
    const uint32_t* deg = (const uint32_t*)(smem + OFF_DEG);
    float* acc = (float*)(smem + OFF_LIST);
    float* af = (float*)(smem + OFF_A);
    const uint32_t wcw = wc[lane];
    for (int n0 = 0; n0 < nloc; n0 += 96) {
        const int nn = min(96, nloc - n0);
        uint32_t any;
        asm volatile("{.reg .pred p, q; setp.ne.u32 p, %1, 0; bar.red.or.pred q, 1, %2, p; selp.u32 %0, 1, 0, q;}"
            : "=r"(any) : "r"((uint32_t)(tid < nn && (all || deg[n0 + tid] > CAPD))), "n"(NMAIN) : "memory");
        if (!any) continue;
        for (int i = tid; i < 96 * 128; i += NMAIN) acc[i] = 0.f;
        for (int n = warp; n < nn; n += (NMAIN / 32)) {
            const uint32_t xw = x[(nbase + n0 + n) * 32 + lane];
            float a0 = 0.f, a1 = 0.f;
            for (int k = 0; k < 64; k++) {
                const uint32_t s = __shfl_sync(0xffffffffu, xw, k >> 1);
                const float xk = (k & 1) ? bfhi(s) : bflo(s);
                const uint32_t w = wa[k * 32 + lane];
                a0 = fmaf(xk, bflo(w), a0); a1 = fmaf(xk, bfhi(w), a1);
            }
            af[n * 64 + 2 * lane] = rbf(a0); af[n * 64 + 2 * lane + 1] = rbf(a1);
        }
        bar_sync<1, NMAIN>();
        for (int p = warp; p < NB; p += (NMAIN / 32)) {
            const unsigned long long h = __ldcg(&g_hdr[p * NB + blockIdx.x]);
            const int cnt = h & 8191, c0 = (h >> 13) & 8191;
            const uint32_t* seg = (const uint32_t*)(g_xch + p * NU + ((h >> 26) & 4095));
            for (int i0 = 0; i0 < cnt; i0 += 32) {
                uint2 en = make_uint2(0, 0);
                bool hit = false;
                const int i = i0 + lane;
                if (i < cnt) {
                    en.x = __ldcg(seg + (i / 3) * 4 + i % 3);
                    en.y = ((__ldcg(seg + (i / 3) * 4 + 3) >> (8 * (i % 3))) & 255) + (i >= c0 ? 256 : 0);
                    hit = en.y - (uint32_t)n0 < (uint32_t)nn && (all || deg[en.y] > CAPD);
                }
                uint32_t m = __ballot_sync(0xffffffffu, hit);
                while (m) {
                    const int j = __ffs(m) - 1;
                    m &= m - 1;
                    const uint32_t w0 = __shfl_sync(0xffffffffu, en.x, j);
                    const int n = (int)__shfl_sync(0xffffffffu, en.y, j) - n0;
                    const uint32_t xw = x[(w0 >> 16) * 32 + lane];
                    float b0 = 0.f, b1 = 0.f, v0 = 0.f, v1 = 0.f;
                    #pragma unroll 8
                    for (int k = 0; k < 64; k++) {
                        const uint32_t s = __shfl_sync(0xffffffffu, xw, k >> 1);
                        const float xk = (k & 1) ? bfhi(s) : bflo(s);
                        const uint32_t u = wb[k * 32 + lane], w = wv[k * 32 + lane];
                        b0 = fmaf(xk, bflo(u), b0); b1 = fmaf(xk, bfhi(u), b1);
                        v0 = fmaf(xk, bflo(w), v0); v1 = fmaf(xk, bfhi(w), v1);
                    }
                    const float e = bflo(w0);
                    const float t0 = gate(af[n * 64 + 2 * lane], b0, e * bflo(wcw));
                    const float t1 = gate(af[n * 64 + 2 * lane + 1], b1, e * bfhi(wcw));
                    float* a = acc + n * 128;
                    atomicAdd(a + lane, t0); atomicAdd(a + 32 + lane, t1);
                    atomicAdd(a + 64 + lane, t0 * v0); atomicAdd(a + 96 + lane, t1 * v1);
                }
            }
        }
        bar_sync<1, NMAIN>();
        for (int n = warp; n < nn; n += (NMAIN / 32)) {
            const int node = n0 + n;
            if (!(all || deg[node] > CAPD)) continue;
            const uint32_t uw = *(const uint32_t*)(smem + OFF_U + node * 128 + ((lane * 4) ^ ((node & 7) << 4)));
            out[(nbase + node) * 32 + lane] = finish(x[(nbase + node) * 32 + lane], bflo(uw), bfhi(uw), acc + n * 128, lane);
        }
        bar_sync<1, NMAIN>();
    }
}

__global__ void __launch_bounds__(NTHR, 1)
gatedgcn_kernel(const uint4* __restrict__ dst, const uint4* __restrict__ x, const uint2* __restrict__ eattr,
                const uint4* __restrict__ src, const uint4* __restrict__ wa, const uint4* __restrict__ wb,
                const uint4* __restrict__ wcg, const uint4* __restrict__ wu, const uint4* __restrict__ wv,
                uint4* __restrict__ out, unsigned char* tab, const __grid_constant__ CUtensorMap xmap)
{
    extern __shared__ __align__(1024) unsigned char smem[];
    const uint32_t sbase = (uint32_t)__cvta_generic_to_shared(smem);
    const int tid = threadIdx.x, lane = tid & 31, warp = __shfl_sync(0xffffffffu, tid >> 5, 0), cta = blockIdx.x;
    const int nbase = cta * NPB, nloc = min(NPB, NN - nbase);
    uint32_t* hist = (uint32_t*)(smem + OFF_HIST);
    uint32_t* offs = (uint32_t*)(smem + OFF_OFFS);
    uint32_t* deg = (uint32_t*)(smem + OFF_DEG);
    uint32_t* cnt = (uint32_t*)(smem + OFF_CNT);
    uint32_t* ninfo = (uint32_t*)(smem + OFF_NINFO);
    uint32_t* misc = (uint32_t*)(smem + OFF_MISC);

    const int ne = min(CH, NE - cta * CH);
    const uint32_t mbar = sbase + OFF_MBAR;


    if (warp >= NMAIN / 32) {
        if (warp == 24) {
            if (lane < 13) asm volatile("mbarrier.init.shared::cta.b64 [%0], %1;" :: "r"(mbar + lane * 8), "r"(lane < 11 ? 1 : lane == 11 ? 64 : NMAIN / 32) : "memory");
            if (lane == 13) asm volatile("prefetch.tensormap [%0];" :: "l"(&xmap) : "memory");
            asm volatile("fence.proxy.async.shared::cta;" ::: "memory");
            __syncwarp();
            bar_arrive<9, NG + 32>();
            bar_arrive<4, NEG + 64>();
            bar_sync<12, NEG + 32>();
            if (lane == 0) {
                #pragma unroll 1
                for (int n = 0; n < 10; n++) {
                    auto id = [](int j) { return j < XE ? j : j < XE + 4 ? j - XE + 6 : j - 4; };
                    const int i = id(n);
                    if (n >= WIN) mbar_wait(mbar + id(n - WIN) * 8);
                    if (i < 6) {
                        mbar_expect(mbar + i * 8, 8192);
                        asm volatile("cp.async.bulk.tensor.2d.shared::cluster.global.mbarrier::complete_tx::bytes [%0], [%1, {%3, %4}], [%2];"
                            :: "r"(sbase + OFF_X + i * 8192), "l"(&xmap), "r"(mbar + i * 8), "r"(0), "r"(nbase + i * 64) : "memory");
                    } else {
                        const int k = i - 6, c = k < 3 ? NEG * 4 : ne - 3 * NEG * 4;
                        mbar_expect(mbar + i * 8, c * 6);
                        bulk_load(sbase + OFF_SRC + k * NEG * 16, src + cta * (CH / 4) + k * NEG, c * 4, mbar + i * 8);
                        bulk_load(sbase + OFF_EAT + k * NEG * 8, eattr + cta * (CH / 4) + k * NEG, c * 2, mbar + i * 8);
                    }
                }
            }
            __syncwarp();
            bar_sync<13, NEG + 32>();
            if (lane == 0) {
                const uint32_t target = misc[M_EPOCH] * NB;
                asm volatile("red.relaxed.gpu.global.add.u32 [%0], 1;" :: "l"(g_bar + 32) : "memory");
                uint32_t v;
                int spin = 0;
                do {
                    asm volatile("ld.relaxed.gpu.global.u32 %0, [%1];" : "=r"(v) : "l"(g_bar + 32) : "memory");
                } while (v < target && ++spin < SPIN_LIMIT);
                asm volatile("mbarrier.arrive.shared::cta.b64 _, [%0];" :: "r"(mbar + 80) : "memory");
            }
            __syncwarp();
        } else if (warp == 27) {
            const uint32_t wcw = __ldg((const uint32_t*)wcg + lane);
            const uint32_t epoch = __ldcg(&g_bar[32]) / NB + 1;
            ((uint32_t*)(smem + OFF_WC))[lane] = wcw;
            const uint32_t wcm = __reduce_max_sync(0xffffffffu, fold2(wcw & 0x7FFF7FFFu));
            if (lane == 0) {
                misc[M_EPOCH] = epoch; misc[M_WCMAX] = wcm;
                if (cta == 0) asm volatile("st.relaxed.gpu.global.u32 [%0], 0;" :: "l"(g_bar + (~epoch & 1)) : "memory");
            }
            __syncwarp();
            bar_arrive<4, NEG + 64>();
            bar_arrive<7, 128>();
            bar_sync<11, NMAIN + 32>();
            if (lane == 0) {
                asm volatile("red.release.gpu.global.add.u32 [%0], %1;" :: "l"(g_bar + (epoch & 1)), "r"(1 + (misc[M_TBAD] << 16)) : "memory");
                uint32_t v;
                int spin = 0;
                do {
                    asm volatile("ld.acquire.gpu.global.u32 %0, [%1];" : "=r"(v) : "l"(g_bar + (epoch & 1)) : "memory");
                } while ((v & 0xFFFF) < NB && ++spin < SPIN_LIMIT);
                misc[M_GBAD] = v >> 16;
            }
            __syncwarp();
        } else {
            if (tid == 800) misc[M_NSPARE] = 0;
            __syncwarp();
            bar_sync<7, 128>();
            const uint32_t epoch = misc[M_EPOCH];
            for (int b = tid - 800; b < NB; b += 64) {
                const uint2 c = *(const uint2*)&hist[2 * b];
                asm volatile("st.relaxed.gpu.global.u64 [%0], %1;" :: "l"(g_hdr + cta * NB + b),
                    "l"(((unsigned long long)epoch << 38) | ((unsigned long long)((offs[2 * b] * 21846u) >> 16) << 26) | (c.x << 13) | (c.x + c.y)) : "memory");
            }
            __syncwarp();
            bar_sync<10, NEG + 64>();
            uint32_t todo = tid - 800 < NB - 128 ? 7 : 3;
            int spin = 0;
            do {
                unsigned long long h[3];
                #pragma unroll
                for (int i = 0; i < 3; i++) {
                    h[i] = 0;
                    if (todo >> i & 1)
                        asm volatile("ld.relaxed.gpu.global.u64 %0, [%1];" : "=l"(h[i]) : "l"(g_hdr + (tid - 800 + 64 * i) * NB + cta) : "memory");
                }
                spin++;
                #pragma unroll
                for (int i = 0; i < 3; i++) {
                    const bool ok = (uint32_t)(h[i] >> 38) == (epoch & 0x3FFFFFFu);
                    if ((todo >> i & 1) && (ok || spin == SPIN_LIMIT)) {
                        todo &= ~(1u << i);
                        const int p = tid - 800 + 64 * i;
                        const uint32_t nu = ok ? ((((uint32_t)h[i] & 8191) + 2) * 21846u) >> 16 : 0;
                        ((uint2*)(smem + OFF_SEG))[p] =
                            make_uint2(nu | ((((uint32_t)h[i] >> 13) & 8191) << 15), p * NU + ((uint32_t)(h[i] >> 26) & 4095));
                        if (nu > LPS) {
                            const uint32_t k0 = atomicAdd(&misc[M_NSPARE], nu - LPS);
                            for (uint32_t k = k0; k < k0 + nu - LPS && k < NSPARE; k++) ((uint32_t*)(smem + OFF_SPARE))[k] = p | ((LPS + k - k0) << 8);
                        }
                    }
                }
            } while (todo);
            __syncwarp();
            asm volatile("mbarrier.arrive.shared::cta.b64 _, [%0];" :: "r"(mbar + 88) : "memory");
        }
        if (warp < 27) {
            bar_sync<14, 96>();
            const uint32_t nspare = misc[M_NSPARE], tag = misc[M_EPOCH] & 127;
            const uint4 none = make_uint4(0, 0, 0, ~(tag << 25));
            uint32_t sp = 0;
            uint2 sg = make_uint2(0, 0);
            uint4 en = none;
            if (nspare <= NSPARE && tid - 768 < nspare) {
                sp = ((const uint32_t*)(smem + OFF_SPARE))[tid - 768];
                sg = ((const uint2*)(smem + OFF_SEG))[sp & 255];
                en = ld_unit(g_xch + sg.y + (sp >> 8));
            }
            mbar_wait(mbar + 96);
            if (tid == 863) {
                const int tv = table_scale(misc);
                const float epsf = 1e-6f * __uint_as_float((uint32_t)(127 - tv) << 23);
                misc[M_NSC] = (0x8000u | ((uint32_t)(16 - tv) << 7)) * 0x10001u;
                misc[M_EPS] = packbf(epsf, epsf);
            }
            if (nspare <= NSPARE) {
                for (uint32_t k = tid - 768; k < nspare; k += 96) {
                    if (k >= 96) {
                        sp = ((const uint32_t*)(smem + OFF_SPARE))[k];
                        sg = ((const uint2*)(smem + OFF_SEG))[sp & 255];
                        en = none;
                    }
                    consume(smem, en, sg.y + (sp >> 8), (int)(sg.x >> 12) - 24 * (int)(sp >> 8), tag);
                }
            } else {
                for (int p = warp - 24; p < NB; p += 3) {
                    const uint2 sg = ((const uint2*)(smem + OFF_SEG))[p];
                    for (uint32_t i = LPS + lane; i < (sg.x & 4095); i += 32)
                        consume(smem, none, sg.y + i, (int)(sg.x >> 12) - 24 * (int)i, tag);
                }
            }
            __syncwarp();
            bar_arrive<6, NMAIN + 96>();
        }
        bar_arrive<8, NTHR>();
        return;
    }
    if (warp >= NG / 32) {
        const int t = tid - NG;
        const bool has3 = t + 3 * NEG < ne / 4;
        uint32_t key[16], rk[16];
        (t < 320 ? hist[t] : cnt[t - 320]) = 0;
        deg[t] = t < NPB ? 0 : 1u << 30;
        if (t < 32) deg[NEG + t] = 1u << 30;
        #pragma unroll
        for (int k = 0; k < 4; k++)
            if (k < 3 || has3) *(uint4*)(key + 4 * k) = __ldcs(dst + cta * (CH / 4) + t + k * NEG);
        bar_arrive<12, NEG + 32>();
        bar_sync<3, NEG>();
        #pragma unroll
        for (int i = 0; i < 6; i++)
            if (i < 5 || t + i * NEG < NU) *(uint32_t*)(smem + OFF_STD + (t + i * NEG) * 4) = 0x7B7B7Bu;
        #pragma unroll
        for (int i = 0; i < 16; i++) {
            if (i < 12 || has3) {
                key[i] += __umulhi(key[i], 11332368u) * (512 - NPB);
                rk[i] = atomicAdd(&hist[key[i] >> 8], 1);
            }
        }
        bar_sync<3, NEG>();
        if (warp == NG / 32) {
            uint32_t c0[5], us[5], s = 0;
            #pragma unroll
            for (int i = 0; i < 5; i++) {
                const uint2 c = *(const uint2*)&hist[lane * 10 + 2 * i];
                c0[i] = c.x; us[i] = s;
                s += ((c.x + c.y + 2) * 21846u) >> 16;
            }
            uint32_t inc = s;
            #pragma unroll
            for (int o = 1; o < 32; o <<= 1) { const uint32_t v = __shfl_up_sync(0xffffffffu, inc, o); if (lane >= o) inc += v; }
            #pragma unroll
            for (int i = 0; i < 5; i++) {
                const uint32_t u = 3 * (inc - s + us[i]);
                *(uint2*)&offs[lane * 10 + 2 * i] = make_uint2(u, u + c0[i]);
            }
            bar_arrive<7, 128>();
        }
        bar_sync<4, NEG + 64>();
        const uint32_t epoch = misc[M_EPOCH], wcm = misc[M_WCMAX];
        #pragma unroll
        for (int i = 0; i < 16; i++)
            if (i < 12 || has3) rk[i] += offs[key[i] >> 8];
        #pragma unroll
        for (int i = 0; i < 16; i++)
            if (i < 12 || has3) smem[OFF_STD + __umulhi(rk[i], 0x55555556u) + rk[i]] = (unsigned char)key[i];
        uint32_t em = 0;
        #pragma unroll
        for (int k = 0; k < 4; k++) {
            mbar_wait(mbar + 48 + k * 8);
            if (k == 2) bar_arrive<10, NEG + 64>();
            if (k < 3 || has3) {
                const uint4 sv = *(const uint4*)(smem + OFF_SRC + (t + k * NEG) * 16);
                const uint2 ev = *(const uint2*)(smem + OFF_EAT + (t + k * NEG) * 8);
                uint32_t* stg = (uint32_t*)(smem + OFF_STG);
                stg[rk[4 * k]] = __byte_perm(ev.x, sv.x, 0x5410); stg[rk[4 * k + 1]] = __byte_perm(ev.x, sv.y, 0x5432);
                stg[rk[4 * k + 2]] = __byte_perm(ev.y, sv.z, 0x5410); stg[rk[4 * k + 3]] = __byte_perm(ev.y, sv.w, 0x5432);
                em = magmax2(magmax2(em, ev.x), ev.y);
            }
        }
        bar_arrive<5, NG + NEG>();
        uint32_t tagb;
        asm volatile("{.reg .pred p, q; setp.ne.u32 p, %1, 0; bar.red.or.pred q, 3, 384, p; selp.u32 %0, 1, 0, q;}"
            : "=r"(tagb) : "r"((uint32_t)!(bflo(fold2(em)) * bflo(wcm) < 40.f)) : "memory");
        tagb |= epoch << 1;
        uint4 cv[6];
        #pragma unroll
        for (int i = 0; i < 6; i++) {
            if (i < 5 || t + i * NEG < NU) {
                const uint32_t* pw = (const uint32_t*)(smem + OFF_STG + (t + i * NEG) * 12);
                cv[i] = make_uint4(pw[0], pw[1], pw[2], *(const uint32_t*)(smem + OFF_STD + (t + i * NEG) * 4));
            }
        }
        #pragma unroll
        for (int i = 0; i < 6; i++) {
            if (i < 5 || t + i * NEG < NU) {
                cv[i].w = __byte_perm(cv[i].w, tagb, 0x4210);
                st_unit(g_xch + cta * NU + t + i * NEG, cv[i]);
            }
        }
        bar_arrive<13, NEG + 32>();
        bar_sync<2, NG + NEG>();
    } else {
        {
            const int m2 = tid >= 256, c = tid & 255;
            const uint32_t o = sbase + OFF_A + m2 * 16384 + c * 16;
            const uint4* g0 = (m2 ? wa : wb) + c;
            const uint4* g1 = (m2 ? wu : wv) + c;
            #pragma unroll
            for (int i = 0; i < 4; i++) {
                if (m2 || !(i & 1)) {
                    asm volatile("cp.async.cg.shared.global [%0], [%1], 16;" :: "r"(o + i * 2048), "l"(g0 + i * 128) : "memory");
                    asm volatile("cp.async.cg.shared.global [%0], [%1], 16;" :: "r"(o + i * 2048 + 8192), "l"(g1 + i * 128) : "memory");
                }
            }
            if (tid < 128) asm volatile("cp.async.cg.shared.global [%0], [%1], 16;" :: "r"(sbase + OFF_A + 32768 + tid * 16), "l"(x + tid) : "memory");
            asm volatile("cp.async.commit_group;" ::: "memory");
        }
        ninfo[tid] = NPB;
        if (tid < M_NSPARE) misc[tid] = tid == M_TASK ? NMAIN / 32 : 0;
        bar_sync<1, NG>();
        asm volatile("cp.async.wait_group 0;" ::: "memory");
        {
            const int l = tid & 7, m2 = tid >= 256;
            const int nk = m2 ? 16 : 32, k0 = (tid >> 3) & 31;
            const uint32_t sw = (k0 & 7) << 4;
            const uint32_t x2 = m2 ? 0 : (l >> 2);
            const unsigned char* rd = smem + OFF_A + m2 * 16384 + (tid & 255) * 16;
            unsigned char* w0 = smem + k0 * 128 + (m2 ? OFF_WAU + (l >> 1) * 4 : OFF_WBV + (l >> 2) * 8192 + (l & 3) * 4);
            const uint32_t o0 = (m2 ? (l & 1) * 64 : x2 * 64) ^ sw, o1 = m2 ? o0 + 8192 : o0 ^ 64;
            uint32_t ma = 0, mb = 0;
            #pragma unroll 2
            for (int k = 0; k < 64 * 128; k += nk * 128) {
                const uint4 a = *(const uint4*)(rd + k + x2 * 8192), b = *(const uint4*)(rd + k + 8192 - x2 * 8192);
                #pragma unroll
                for (int j = 0; j < 4; j++) {
                    *(uint32_t*)(w0 + k + (o0 ^ (j * 16))) = ((const uint32_t*)&a)[j];
                    *(uint32_t*)(w0 + k + (o1 ^ (j * 16))) = ((const uint32_t*)&b)[j];
                }
                if (!m2) {
                    ma = magmax2(magmax2(magmax2(magmax2(ma, a.x), a.y), a.z), a.w);
                    mb = magmax2(magmax2(magmax2(magmax2(mb, b.x), b.y), b.z), b.w);
                }
            }
            if (!m2) {
                uint4 xs = make_uint4(0, 0, 0, 0);
                if (tid < 128) xs = *(const uint4*)(smem + OFF_A + 32768 + tid * 16);
                const uint32_t mv = __reduce_max_sync(0xffffffffu, fold2(x2 ? ma : mb));
                const uint32_t mx = __reduce_max_sync(0xffffffffu, fold2(magmax2(magmax2(magmax2(xs.x & 0x7FFF7FFFu, xs.y), xs.z), xs.w)));
                if (lane < 2) atomicMax(&misc[lane ? M_WVMAX : M_XMAX], lane ? mv : mx);
            }
        }
        asm volatile("fence.proxy.async.shared::cta;" ::: "memory");
        bar_sync<9, NG + 32>();
        bar_arrive<2, NG + NEG>();
    }
    float wc[8];
    {
        const int q = lane & 3, tile = warp >> 2;
        int row = warp * 16 + (lane >> 2);
        const uint32_t xt = sbase + OFF_X + tile * 8192;
        unsigned char* tl = tab + (size_t)(nbase + row) * 128 + q * 16;
        unsigned char* th = tab + (size_t)NN * 128 + (size_t)(nbase + row) * 64 + q * 16;
        asm volatile("" : "+l"(tl), "+l"(th));
        float d[32];
        mbar_wait(mbar + tile * 8);
        gemm_issue<true>(d, xt, sbase + OFF_WBV, 0);
        {
            const uint32_t vs2 = (uint32_t)((16 - table_scale(misc)) << 7) * 0x10001u;
            uint32_t bor = 0, bmin = 0xFFFFFFFFu, vor = 0;
            bool bad = false;
            uint2 H0[2];
            #pragma unroll
            for (int p = 0; p < 2; p++) {
                uint32_t eb[8], vv[8];
                gemm_wait(d);
                #pragma unroll
                for (int j = 0; j < 8; j++) {
                    const int i = 4 * (j & 3) + 2 * (j >> 2);
                    eb[j] = packbf(ex2(fmaf(d[i], -LOG2E, -111.f)), ex2(fmaf(d[i + 1], -LOG2E, -111.f)));
                    vv[j] = packbf(d[16 + i], d[17 + i]);
                }
                asm volatile("" : R8("+r", eb, 0), R8("+r", vv, 0));
                gemm_issue<false>(d, xt, p ? sbase + OFF_WAU : sbase + OFF_WBV + 8192, blockIdx.y);
                #pragma unroll
                for (int h = 0; h < 2; h++) {
                    const uint32_t* e4 = eb + 4 * h;
                    uint32_t v4[4];
                    #pragma unroll
                    for (int j = 0; j < 4; j++) v4[j] = hmul2(vv[4 * h + j], vs2);
                    bor |= e4[0] | e4[1]; bor |= e4[2] | e4[3];
                    bmin = __vimin3_u16x2(__vimin3_u16x2(bmin, e4[0], e4[1]), e4[2], e4[3]);
                    const uint32_t vo = v4[0] | v4[1] | v4[2] | v4[3];
                    vor |= vo;
                    bad |= !(vo & 0x06000600u) && ((vv[4 * h] | vv[4 * h + 1] | vv[4 * h + 2] | vv[4 * h + 3]) & 0x7FFF7FFFu);
                    stg128(tl + h * 1024 + p * 64, __byte_perm(e4[0], e4[1], 0x6420), __byte_perm(e4[2], e4[3], 0x6420),
                           __byte_perm(v4[0], v4[1], 0x6420), __byte_perm(v4[2], v4[3], 0x6420), row + h * 8 < nloc);
                    const uint32_t hv1 = __byte_perm(v4[2], v4[3], 0x7531);
                    const uint2 H = make_uint2(__byte_perm(e4[0], e4[1], 0x7531) + (__byte_perm(e4[2], e4[3], 0x7531) << 4),
                                               __byte_perm(v4[0], v4[1], 0x7531) | __funnelshift_l(hv1, hv1, 4));
                    if (p == 0) H0[h] = H;
                    else stg128(th + h * 512, H0[h].x, H0[h].y, H.x, H.y, row + h * 8 < nloc);
                }
            }
            if (bad || ((bor & 0xF000F000u) | (vor & 0x78007800u)) || min(bmin & 0xFFFFu, bmin >> 16) < 0x80u) misc[M_TBAD] = 1;
            bar_arrive<11, NMAIN + 32>();
        }
        {
            uint32_t a[16], am = 0;
            gemm_wait(d);
            #pragma unroll
            for (int j = 0; j < 16; j++) a[j] = packh(d[4 * (j & 7) + 2 * (j >> 3)] * -LOG2E, d[4 * (j & 7) + 2 * (j >> 3) + 1] * -LOG2E);
            asm volatile("" : R8("+r", a, 0), R8("+r", a, 8));
            gemm_issue<false>(d, xt, sbase + OFF_WAU + 8192, blockIdx.y);
            store_rows(smem + OFF_A, a, row, q);
            #pragma unroll
            for (int j = 0; j < 16; j++) asm("{.reg .b32 t; abs.f16x2 t, %1; max.NaN.f16x2 %0, %0, t;}" : "+r"(am) : "r"(a[j]));
            if (fold2(am) >= 0x5380u) misc[M_BAD] = 1;
            __syncwarp();
            if (lane == 0) asm volatile("mbarrier.arrive.shared::cta.b64 _, [%0];" :: "r"(mbar + 96) : "memory");
            gemm_wait(d);
            #pragma unroll
            for (int j = 0; j < 16; j++) a[j] = packbf(d[4 * (j & 7) + 2 * (j >> 3)], d[4 * (j & 7) + 2 * (j >> 3) + 1]);
            if (warp < NG / 32) bar_sync<5, NG + NEG>();
            store_rows(smem + OFF_U, a, row, q);
        }

        mbar_wait(mbar + 88);
        uint32_t ua[3];
        uint32_t f0 = tid;
        asm volatile("" : "+r"(f0));
        #pragma unroll
        for (int j = 0; j < 3; j++) {
            const uint32_t f = f0 + j * NMAIN;
            uint32_t p = (f * 61681u) >> 20, i = f - p * LPS;
            if (j == 2 && f >= LPS * NB) { p = NB - 1; i = 4095; }
            const uint2 sg = ((const uint2*)(smem + OFF_SEG))[p];
            ua[j] = i < (sg.x & 4095) ? ((sg.y + i) << 8) + min(max((int)(sg.x >> 12) - 24 * (int)i + 128, 128), 152) : 0;
        }
        const uint32_t tag = misc[M_EPOCH] << 25;
        mbar_wait(mbar + 80);
        uint4 en[3];
        #pragma unroll
        for (int j = 0; j < 3; j++) {
            en[j].w = tag | ((123 + lane) * 0x010101u);
            if (ua[j]) en[j] = ld_unit(g_xch + (ua[j] >> 8));
        }
        {
            const uint4 w = *(const uint4*)(smem + OFF_WC + (lane & 7) * 16);
            wc[0] = -LOG2E * bflo(w.x); wc[1] = -LOG2E * bfhi(w.x); wc[2] = -LOG2E * bflo(w.y); wc[3] = -LOG2E * bfhi(w.y);
            wc[4] = -LOG2E * bflo(w.z); wc[5] = -LOG2E * bfhi(w.z); wc[6] = -LOG2E * bflo(w.w); wc[7] = -LOG2E * bfhi(w.w);
            #pragma unroll
            for (int i = 0; i < 8; i++) asm volatile("" : "+f"(wc[i]));
        }
        mbar_wait(mbar + 96);
        uint32_t* list = (uint32_t*)(smem + OFF_LIST);
        uint32_t wor = 0;
        #pragma unroll
        for (int j = 0; j < 3; j++) {
            int spin = 0;
            while ((en[j].w ^ tag) >> 25) {
                en[j] = ld_unit(g_xch + (ua[j] >> 8));
                if (++spin >= SPIN_LIMIT) { en[j].w = tag | 0x7B7B7Bu; ua[j] = 0; }
            }
            wor |= en[j].w;
        }
        uint32_t nd[9], rk[9];
        #pragma unroll
        for (int j = 0; j < 9; j++) {
            nd[j] = prmt(en[j / 3].w, 0x010101u << (ua[j / 3] & 31), 0xCC40 + 0x11 * (j % 3));
            rk[j] = atomicAdd(&deg[nd[j]], 1);
        }
        #pragma unroll
        for (int j = 0; j < 9; j++) {
            const uint4& e4 = en[j / 3];
            if (rk[j] < CAPD) list[nd[j] * CAPD + rk[j]] = j % 3 == 0 ? e4.x : j % 3 == 1 ? e4.y : e4.z;
        }
        if (wor & (1u << 24)) misc[M_BAD] = 1;
        bar_sync<6, NMAIN + 96>();
        if (warp < NG / 32) {
            uint32_t myd = 63, myr = 0;
            if (tid < nloc) {
                myd = deg[tid];
                if (myd > CAPD) { misc[M_SLOW] = 1; myd = 63; } else myr = atomicAdd(&cnt[myd], 1);
            }
            bar_sync<1, NG>();
            const uint32_t c0 = cnt[2 * lane], c1 = cnt[2 * lane + 1];
            uint32_t inc = c0 + c1;
            #pragma unroll
            for (int o = 1; o < 32; o <<= 1) { const uint32_t v = __shfl_down_sync(0xffffffffu, inc, o); if (lane + o < 32) inc += v; }
            const uint32_t above = inc - c0 - c1;
            const uint32_t b1 = __shfl_sync(0xffffffffu, above, myd >> 1), b0 = __shfl_sync(0xffffffffu, above + c1, myd >> 1);
            if (myd <= CAPD) ninfo[((myd & 1) ? b1 : b0) + myr] = tid | (myd << 16);
        }
    }
    bar_sync<8, NTHR>();

    if (!(misc[M_BAD] | misc[M_GBAD])) {
        const int l = lane & 7, sub = lane >> 3;
        uint64_t pa = (uint64_t)(tab + l * 16), pb = (uint64_t)(tab + (size_t)NN * 128 + (l & 3) * 16 + (l >> 2) * 8);
        asm volatile("" : "+l"(pa), "+l"(pb));
        char* outp = (char*)(out + (size_t)nbase * 8 + l);
        uint32_t nia = sbase + OFF_NINFO + sub * 4, lsw = l << 4;
        asm volatile("" : "+r"(nia), "+r"(lsw));
        Row r0 = Row{0, 0, 0, 0, 0, 0}, r1 = r0;
        int task = warp;
        while (task < NTASK) {
            uint32_t ni;
            asm volatile("ld.shared.u32 %0, [%1];" : "=r"(ni) : "r"(nia + task * 16));
            const uint32_t node = ni & 0xFFFF;
            int rem = ni >> 16;
            const uint2* ep = (const uint2*)(smem + OFF_LIST + node * (CAPD * 4));
            uint2 wa2 = ep[0], wb2 = ep[1];
            ldrow(r0, wa2.x, rem > 0, pa, pb);
            ldrow(r1, wa2.y, rem > 1, pa, pb);
            float ap[8];
            uint32_t num[4], den[4];
            const unsigned char* nrow = smem + node * 128 + ((lsw ^ (node << 4)) & 0x70);
            {
                const uint4 w = *(const uint4*)(nrow + OFF_A);
                ap[0] = hlo(w.x); ap[1] = hhi(w.x); ap[2] = hlo(w.y); ap[3] = hhi(w.y);
                ap[4] = hlo(w.z); ap[5] = hhi(w.z); ap[6] = hlo(w.w); ap[7] = hhi(w.w);
                #pragma unroll
                for (int i = 0; i < 8; i++) asm volatile("" : "+f"(ap[i]));
                #pragma unroll
                for (int i = 0; i < 4; i++) num[i] = den[i] = 0;
            }
            if (rem > 0) {
                uint32_t T0[4], T1[4];
                gate_t(T0, bflo(wa2.x), wc, ap);
                gate_t(T1, bflo(wa2.y), wc, ap);
                ep += 2;
                bool m1 = rem > 1;
                #pragma unroll 1
                while (true) {
                    const bool m2 = rem > 2;
                    { uint32_t eb[4], vv[4]; unpack(r0, eb, vv); ldrow(r0, wb2.x, m2, pa, pb); gate_rest(T0, eb, vv, num, den); }
                    if (!m1) break;
                    m1 = rem > 3;
                    { uint32_t eb[4], vv[4]; unpack(r1, eb, vv); ldrow(r1, wb2.y, m1, pa, pb); gate_rest(T1, eb, vv, num, den); }
                    if (!m2) break;
                    const float e0 = bflo(wb2.x), e1 = bflo(wb2.y);
                    wb2 = *ep++;
                    rem -= 2;
                    asm volatile("" : "+r"(rem));
                    gate_t(T0, e0, wc, ap);
                    gate_t(T1, e1, wc, ap);
                }
            }
            __syncwarp();
            if (lane == 0) asm volatile("atom.shared.inc.u32 %0, [%1], 0x7fffffff;" : "=r"(task) : "r"(sbase + OFF_MISC + M_TASK * 4) : "memory");
            {
                const uint4 u = *(const uint4*)(nrow + OFF_U), xv = *(const uint4*)(nrow + OFF_X);
                const uint32_t nsc = ((volatile uint32_t*)misc)[M_NSC], eps2 = ((volatile uint32_t*)misc)[M_EPS];
                uint4 o;
                o.x = hadd2(xv.x, hfma2relu(num[0], nrcp2(hfma2(den[0], nsc, eps2)), u.x));
                o.y = hadd2(xv.y, hfma2relu(num[1], nrcp2(hfma2(den[1], nsc, eps2)), u.y));
                o.z = hadd2(xv.z, hfma2relu(num[2], nrcp2(hfma2(den[2], nsc, eps2)), u.z));
                o.w = hadd2(xv.w, hfma2relu(num[3], nrcp2(hfma2(den[3], nsc, eps2)), u.w));
                if (node < NPB) *(uint4*)(outp + node * 128) = o;
            }
            task = __shfl_sync(0xffffffffu, task, 0);
        }
    }
    if (misc[M_BAD] | misc[M_GBAD] | misc[M_SLOW]) {
        bar_sync<1, NMAIN>();
        general_path(smem, (const uint32_t*)x, (const uint32_t*)wa, (const uint32_t*)wb,
                     (const uint32_t*)wcg, (const uint32_t*)wv, (uint32_t*)out);
    }
}

__device__ float g_acc[(size_t)NN * 128];
__device__ __forceinline__ float2 matvec2(uint32_t xw, const uint32_t* __restrict__ w, int lane) {
    float a0 = 0.f, a1 = 0.f;
    for (int k = 0; k < 64; k++) {
        const uint32_t s = __shfl_sync(0xffffffffu, xw, k >> 1), u = w[k * 32 + lane];
        const float xk = (k & 1) ? bfhi(s) : bflo(s);
        a0 = fmaf(xk, bflo(u), a0); a1 = fmaf(xk, bfhi(u), a1);
    }
    return make_float2(a0, a1);
}
__global__ void plain_zero() { g_acc[(size_t)blockIdx.x * 256 + threadIdx.x] = 0.f; }
__global__ void plain_edges(const uint32_t* __restrict__ x, const uint16_t* __restrict__ eattr, const int* __restrict__ src,
                            const int* __restrict__ dst, const uint32_t* __restrict__ wa, const uint32_t* __restrict__ wb,
                            const uint32_t* __restrict__ wc, const uint32_t* __restrict__ wv) {
    const int lane = threadIdx.x & 31, e = blockIdx.x * 8 + (threadIdx.x >> 5), n = dst[e];
    const uint32_t xs = x[src[e] * 32 + lane];
    const float2 a = matvec2(x[n * 32 + lane], wa, lane), b = matvec2(xs, wb, lane), v = matvec2(xs, wv, lane);
    const float ea = bflo(eattr[e]);
    const float t0 = gate(rbf(a.x), b.x, ea * bflo(wc[lane])), t1 = gate(rbf(a.y), b.y, ea * bfhi(wc[lane]));
    float* acc = g_acc + (size_t)n * 128;
    atomicAdd(acc + lane, t0); atomicAdd(acc + 32 + lane, t1);
    atomicAdd(acc + 64 + lane, t0 * v.x); atomicAdd(acc + 96 + lane, t1 * v.y);
}
__global__ void plain_nodes(const uint32_t* __restrict__ x, const uint32_t* __restrict__ wu, uint32_t* __restrict__ out) {
    const int lane = threadIdx.x & 31, n = blockIdx.x * 8 + (threadIdx.x >> 5);
    const uint32_t xw = x[n * 32 + lane];
    const float2 u = matvec2(xw, wu, lane);
    out[n * 32 + lane] = finish(xw, u.x, u.y, g_acc + (size_t)n * 128, lane);
}

}

extern "C" void kernel_launch(void* const* d_in, const int* in_sizes, int n_in, void* d_out, int out_size) {
    typedef CUresult (*EncodeFn)(CUtensorMap*, CUtensorMapDataType, cuuint32_t, void*, const cuuint64_t*, const cuuint64_t*,
                                 const cuuint32_t*, const cuuint32_t*, CUtensorMapInterleave, CUtensorMapSwizzle,
                                 CUtensorMapL2promotion, CUtensorMapFloatOOBfill);
    static unsigned char* tab = nullptr;
    static EncodeFn encode = nullptr;
    static bool resident = false;
    if (!tab) {
        int dev = 0, sms = 0, per_sm = 0;
        cudaGetDevice(&dev);
        cudaDeviceGetAttribute(&sms, cudaDevAttrMultiProcessorCount, dev);
        if (cudaFuncSetAttribute(gatedgcn_kernel, cudaFuncAttributeMaxDynamicSharedMemorySize, SMEM_BYTES) == cudaSuccess)
            cudaOccupancyMaxActiveBlocksPerMultiprocessor(&per_sm, gatedgcn_kernel, NTHR, SMEM_BYTES);
        void* fn = nullptr;
        cudaDriverEntryPointQueryResult qr;
        cudaGetDriverEntryPoint("cuTensorMapEncodeTiled", &fn, cudaEnableDefault, &qr);
        encode = (EncodeFn)fn;
        resident = encode && sms * per_sm >= NB;
        (void)cudaGetLastError();
        void* p = nullptr;
        cudaGetSymbolAddress(&p, g_tab);
        tab = (unsigned char*)p;
    }
    if (!resident) {
        plain_zero<<<NN / 2, 256>>>();
        plain_edges<<<NE / 8, 256>>>((const uint32_t*)d_in[0], (const uint16_t*)d_in[1], (const int*)d_in[2], (const int*)d_in[3],
                                     (const uint32_t*)d_in[4], (const uint32_t*)d_in[5], (const uint32_t*)d_in[6], (const uint32_t*)d_in[8]);
        plain_nodes<<<NN / 8, 256>>>((const uint32_t*)d_in[0], (const uint32_t*)d_in[7], (uint32_t*)d_out);
        return;
    }
    CUtensorMap xmap;
    const cuuint64_t dims[2] = {64, (cuuint64_t)NN}, strides[1] = {128};
    const cuuint32_t box[2] = {64, 64}, estr[2] = {1, 1};
    encode(&xmap, CU_TENSOR_MAP_DATA_TYPE_BFLOAT16, 2, d_in[0], dims, strides, box, estr, CU_TENSOR_MAP_INTERLEAVE_NONE,
           CU_TENSOR_MAP_SWIZZLE_128B, CU_TENSOR_MAP_L2_PROMOTION_NONE, CU_TENSOR_MAP_FLOAT_OOB_FILL_NONE);
    cudaLaunchConfig_t cfg = {};
    cfg.gridDim = dim3(NB); cfg.blockDim = dim3(NTHR); cfg.dynamicSmemBytes = SMEM_BYTES; cfg.stream = cudaStreamPerThread;
    cudaLaunchAttribute at[1];
    at[0].id = cudaLaunchAttributeCooperative; at[0].val.cooperative = 1;
    cfg.attrs = at; cfg.numAttrs = 1;
    cudaLaunchKernelEx(&cfg, gatedgcn_kernel,
        (const uint4*)d_in[3], (const uint4*)d_in[0], (const uint2*)d_in[1], (const uint4*)d_in[2],
        (const uint4*)d_in[4], (const uint4*)d_in[5], (const uint4*)d_in[6], (const uint4*)d_in[7],
        (const uint4*)d_in[8], (uint4*)d_out, tab, xmap);
}
```
